```python
import torch

def _softmax(x, axis=-1):
    return torch.softmax(x, dim=axis)
def _gelu(x):
    return torch.nn.functional.gelu(x, approximate="tanh")
def _silu(x):
    return torch.nn.functional.silu(x)
def _sigmoid(x):
    return torch.sigmoid(x)
def _layernorm(x, axis=-1, eps=1e-5):
    m = x.mean(dim=axis, keepdim=True)
    v = x.var(dim=axis, keepdim=True, unbiased=False)
    return (x - m) / torch.sqrt(v + eps)
def _scatter_add(tgt, idx, src, axis=0):
    return tgt.clone().index_add_(axis, idx, src)
def _segment_sum(src, seg, n):
    out = torch.zeros((n,) + src.shape[1:], dtype=src.dtype)
    return out.index_add_(0, seg, src)
def _pad(x, pw):
    flat = tuple(v for pair in reversed(pw) for v in pair)
    return torch.nn.functional.pad(x, flat)

kernel_name = 'recurrent_scan__ssm_conv_s5__dense_activation_mish__prompt'

def setup_inputs():

    _w = (lambda a: (lambda t: t.to(torch.bfloat16) if t.is_floating_point() else t)(torch.as_tensor(a)))
    def _A_setup():
        B, S, D = 1, 2048, 512
        P = D
        Lambda_re = -0.5 * (lambda _x: torch.exp(torch.as_tensor(_x)))((lambda *s: torch.randn(*s, dtype=torch.bfloat16) * 0.4)(P))
        Lambda_im = (lambda *s: torch.randn(*s, dtype=torch.bfloat16) * 0.8)(P) * 1.0
        B_re = (lambda *s: torch.randn(*s, dtype=torch.bfloat16) * 0.4)(P, D) * (D ** -0.5)
        B_im = (lambda *s: torch.randn(*s, dtype=torch.bfloat16) * 0.4)(P, D) * (D ** -0.5)
        C_re = (lambda *s: torch.randn(*s, dtype=torch.bfloat16) * 0.4)(D, P) * (P ** -0.5)
        C_im = (lambda *s: torch.randn(*s, dtype=torch.bfloat16) * 0.4)(D, P) * (P ** -0.5)
        log_dt = (lambda *s: torch.randn(*s, dtype=torch.bfloat16) * 0.4)(P) * 0.3 - 2.0
        Dskip = (lambda *s: torch.randn(*s, dtype=torch.bfloat16) * 0.2)(D)
        return {
            "x": _w((lambda *s: torch.randn(*s, dtype=torch.bfloat16) * 0.05)(B, S, D)),
            "Lambda_re": _w(Lambda_re),
            "Lambda_im": _w(Lambda_im),
            "B_re": _w(B_re),
            "B_im": _w(B_im),
            "C_re": _w(C_re),
            "C_im": _w(C_im),
            "log_dt": _w(log_dt),
            "Dskip": _w(Dskip),
        }
    _A_in = _A_setup()

    def _B_setup():
        B, S, D, F = 1, 2048, 512, 1376
        return {
            "x": _w((lambda *s: torch.randn(*s, dtype=torch.bfloat16) * 0.05)(B, S, D)),
            "w1": _w((lambda *s: torch.randn(*s, dtype=torch.bfloat16) * 0.8)(D, F) * (D ** -0.5)),
            "b1": _w((lambda *s: torch.randn(*s, dtype=torch.bfloat16) * 0.2)(F)),
            "w2": _w((lambda *s: torch.randn(*s, dtype=torch.bfloat16) * 0.1)(F, D) * (F ** -0.5)),
        }
    _B_in = _B_setup()

    return {
        "A_x": _A_in["x"],
        "A_Lambda_re": _A_in["Lambda_re"],
        "A_Lambda_im": _A_in["Lambda_im"],
        "A_B_re": _A_in["B_re"],
        "A_B_im": _A_in["B_im"],
        "A_C_re": _A_in["C_re"],
        "A_C_im": _A_in["C_im"],
        "A_log_dt": _A_in["log_dt"],
        "A_Dskip": _A_in["Dskip"],
        "B_x": _B_in["x"],
        "B_w1": _B_in["w1"],
        "B_b1": _B_in["b1"],
        "B_w2": _B_in["w2"],
    }

def reference(A_x, A_Lambda_re, A_Lambda_im, A_B_re, A_B_im, A_C_re, A_C_im, A_log_dt, A_Dskip, B_x, B_w1, B_b1, B_w2):
    def _A_ref(x, Lambda_re, Lambda_im, B_re, B_im, C_re, C_im, log_dt, Dskip):
        Bsz, L, H = x.shape
        Lam = Lambda_re + 1j * Lambda_im
        Bmat = B_re + 1j * B_im
        Cmat = C_re + 1j * C_im
        dt = torch.exp(log_dt)
        Lam_bar = torch.exp(dt * Lam)
        B_bar = ((Lam_bar - 1.0) / Lam)[:, None] * Bmat
        Bu = torch.einsum("bld,pd->blp", x + 0j, B_bar)
        h = torch.zeros_like(Bu[:, 0, :])
        hs = []
        for t in range(L):
            h = Lam_bar[None, :] * h + Bu[:, t, :]
            hs.append(h)
        hseq = torch.stack(hs, 1)
        y = 2.0 * torch.einsum("blp,dp->bld", hseq, Cmat).real + x * Dskip[None, None, :]
        return y

    def _B_ref(x, w1, b1, w2):
        h = torch.einsum("bsd,df->bsf", x, w1) + b1
        sp = torch.log1p(torch.exp(-torch.abs(h))) + torch.where(h > 0, h, torch.zeros_like(h))
        act = h * torch.tanh(sp)
        return torch.einsum("bsf,fd->bsd", act, w2)

    x = A_x
    xn = _layernorm(x, axis=-1)
    s = _A_ref(xn, A_Lambda_re, A_Lambda_im, A_B_re, A_B_im, A_C_re, A_C_im, A_log_dt, A_Dskip)
    g = _silu(_B_ref(xn, B_w1, B_b1, B_w2))
    return x + s * g
```

```cpp
#include <cuda_runtime.h>
#include <cuda.h>
#include <cuda_bf16.h>
#include <stdint.h>

namespace {

typedef __nv_bfloat16 bf16;

struct alignas(64) Maps { CUtensorMap x, b, w1, w2, cre, cim, out; };
struct Params {
  const bf16 *x, *lam_re, *lam_im, *b_lo, *b_hi, *log_dt, *dskip, *w1, *b1, *w2, *c_re, *c_im;
  float* out;
  unsigned long long dsw, dsw8k, dns, dext;
  int swapB, zero;
};

__device__ uint4    g_act[16 * 38 * 1024];
__device__ uint2    g_E[16 * 512];
__device__ uint2    g_rs[512];
__device__ uint32_t g_cs[4 * 1536];
__device__ uint2    g_st[2048];
__device__ uint32_t g_cnt[16 * 32];
__device__ ulonglong2 g_go;
__device__ uint32_t g_epoch[128];
#define TS(role, i)
#define TSW(role)
#define TS0()
#define TSD(role,i,dep)
#define TSX(role, i)

constexpr uint32_t SM_RING = 131072, SM_STG = 212992, SM_MISC = 229376, SM_TOTAL = 232448;
constexpr uint32_t B_XFULL = 0, B_FULL = 64, B_EMPTY = 128, B_JOB = 192, B_FREE = 232, B_E1 = 240, B_LOCK = 280, B_F1 = 328, B_RDY = 368, B_TAG = 400, B_CS = 408, B_GO = 416, B_STAT = 424;
constexpr uint32_t MS_TAG = 432;
constexpr int NB_JOB = 4, NB_STG = 10, NB_FREE = 15;
constexpr uint32_t MS_RL = 512;
constexpr uint32_t MS_EXT = 1024;
constexpr uint32_t SM_S4 = SM_RING + 4 * 16384;
__host__ __device__ constexpr uint32_t slotB(int i) { return i < 6 ? i * 16384 : SM_RING + (i - 5) * 16384; }
__host__ __device__ constexpr uint32_t slotA(int i) { return i < 6 ? SM_RING + (i < 2 ? 4 : i < 4 ? 3 : 0) * 16384 + (i & 1) * 8192 : i * 16384; }
constexpr int SPIN_LIMIT = 1 << 22;
constexpr float LOG2E = 1.4426950408889634f;
#define PROMO CU_TENSOR_MAP_L2_PROMOTION_L2_128B
#define HTRIG 1
#define POLITE 2
#define HEARLY 80
#define PACEB 300
#define PPOS 14
#define WARM 0
#define TANH 1
#define SKPOL 0
#define DPOLL 0
#define HSPLIT 1
#define J1POS 1
constexpr int J1N = J1POS < 0 ? 256 : 512;
#define RELK 2
#define MHOLD 0
#define GONS 2850
#define CPOLL 0
#define PACE 150
#define J0POS 4
#define CSTRIG 2
#define CDELAY 0
#define PFTRIG 0

__device__ __forceinline__ void mbar_init(uint32_t bar, uint32_t cnt) { asm volatile("mbarrier.init.shared::cta.b64 [%0], %1;" ::"r"(bar), "r"(cnt)); }
__device__ __forceinline__ void mbar_expect(uint32_t bar, uint32_t bytes) { asm volatile("mbarrier.arrive.expect_tx.shared::cta.b64 _, [%0], %1;" ::"r"(bar), "r"(bytes) : "memory"); }
__device__ __forceinline__ void mbar_arrive(uint32_t bar) { asm volatile("mbarrier.arrive.shared::cta.b64 _, [%0];" ::"r"(bar) : "memory"); }
__device__ __forceinline__ void mbar_arrive_n(uint32_t bar, uint32_t n) { asm volatile("mbarrier.arrive.shared::cta.b64 _, [%0], %1;" ::"r"(bar), "r"(n) : "memory"); }
template <int N> __device__ __forceinline__ void warp_arrive(uint32_t bar) {
  asm volatile("{ .reg .pred p; elect.sync _|p, 0xffffffff; @p mbarrier.arrive.shared::cta.b64 _, [%0], %1; }" ::"r"(bar), "n"(N) : "memory");
}
__device__ __forceinline__ void warp_arrive_n(uint32_t bar, uint32_t n) {
  asm volatile("{ .reg .pred p; elect.sync _|p, 0xffffffff; @p mbarrier.arrive.shared::cta.b64 _, [%0], %1; }" ::"r"(bar), "r"(n) : "memory");
}
template <int N> __device__ __forceinline__ void warp_arrive_if(uint32_t bar, bool c) {
  asm volatile("{ .reg .pred p, q; elect.sync _|p, 0xffffffff; setp.ne.and.u32 q, %2, 0, p; @q mbarrier.arrive.shared::cta.b64 _, [%0], %1; }" ::"r"(bar), "n"(N), "r"((uint32_t)c) : "memory");
}
__device__ __forceinline__ void mbar_wait(uint32_t bar, uint32_t par) {
  asm volatile(
      "{ .reg .pred p; .reg .u32 n;\n"
      "mbarrier.try_wait.parity.shared::cta.b64 p, [%0], %1;\n"
      "@p bra D;\n"
      "mov.u32 n, 0;\n"
      "W: mbarrier.try_wait.parity.shared::cta.b64 p, [%0], %1;\n"
      "@p bra D;\n"
      "add.u32 n, n, 1; setp.lt.u32 p, n, 4000000; @p bra W;\n"
      "trap;\n"
      "D: }" ::"r"(bar), "r"(par) : "memory");
}
__device__ __forceinline__ void nb_sync(int id, int n) { asm volatile("bar.sync %0, %1;" ::"r"(id), "r"(n) : "memory"); }
__device__ __forceinline__ void nb_arrive(int id, int n) { asm volatile("bar.arrive %0, %1;" ::"r"(id), "r"(n) : "memory"); }
__device__ __forceinline__ void sched_fence() { asm volatile("pmevent 0;" ::: "memory"); }
__device__ __forceinline__ void wg_fence() { asm volatile("wgmma.fence.sync.aligned;" ::: "memory"); }
__device__ __forceinline__ void wg_commit() { asm volatile("wgmma.commit_group.sync.aligned;" ::: "memory"); }
template <int N> __device__ __forceinline__ void wg_wait() { asm volatile("wgmma.wait_group.sync.aligned %0;" ::"n"(N) : "memory"); }
template <int N> __device__ __forceinline__ void pin(float (&d)[N]) {
#pragma unroll
  for (int i = 0; i < N; i++) asm volatile("" : "+f"(d[i])::"memory");
}
constexpr uint32_t SM_BASE = 1024;
__host__ __device__ constexpr uint32_t dlo(uint32_t off, uint32_t lbo) { return ((SM_BASE + off) >> 4) | ((lbo >> 4) << 16); }
constexpr uint32_t H128 = (1024 >> 4) | (1u << 30), HN128 = 128 >> 4;
__device__ __forceinline__ bool elect_one() {
  uint32_t pred = 0, l = 0;
  asm volatile("{ .reg .b32 rx; .reg .pred px; elect.sync rx|px, %2; @px mov.s32 %1, 1; mov.s32 %0, rx; }" : "+r"(l), "+r"(pred) : "r"(0xFFFFFFFFu));
  return pred;
}
__device__ __forceinline__ uint32_t pack2(float lo, float hi) { uint32_t r; asm("cvt.rn.bf16x2.f32 %0, %1, %2;" : "=r"(r) : "f"(hi), "f"(lo)); return r; }
__device__ __forceinline__ float bflo(uint32_t v) { return __uint_as_float(v << 16); }
__device__ __forceinline__ float bfhi(uint32_t v) { return __uint_as_float(v & 0xffff0000u); }
__device__ __forceinline__ float bfround(float v) { return __bfloat162float(__float2bfloat16_rn(v)); }
__device__ __forceinline__ float ex2f(float x) { float y; asm("ex2.approx.ftz.f32 %0, %1;" : "=f"(y) : "f"(x)); return y; }
__device__ __forceinline__ float rcpf(float x) { float y; asm("rcp.approx.ftz.f32 %0, %1;" : "=f"(y) : "f"(x)); return y; }
__device__ __forceinline__ float tanhf_hw(float x) { float y; asm("tanh.approx.f32 %0, %1;" : "=f"(y) : "f"(x)); return y; }
__device__ __forceinline__ void st_ll64(uint2* p, uint32_t a, uint32_t b) {
  asm volatile("{ .reg .b64 u; mov.b64 u, {%1,%2}; st.relaxed.gpu.global.b64 [%0], u; }" ::"l"(p), "r"(a), "r"(b) : "memory");
}
__device__ __forceinline__ uint2 ld_ll64(const uint2* p) {
  uint2 r;
  asm volatile("{ .reg .b64 u; ld.relaxed.gpu.global.b64 u, [%2]; mov.b64 {%0,%1}, u; }" : "=r"(r.x), "=r"(r.y) : "l"(p) : "memory");
  return r;
}
__device__ __forceinline__ void st_ll32(uint32_t* p, uint32_t v) { asm volatile("st.relaxed.gpu.global.u32 [%0], %1;" ::"l"(p), "r"(v) : "memory"); }
__device__ __forceinline__ uint32_t ld_ll32(const uint32_t* p) { uint32_t v; asm volatile("ld.relaxed.gpu.global.u32 %0, [%1];" : "=r"(v) : "l"(p) : "memory"); return v; }
__device__ __forceinline__ float4 lds128f(uint32_t a) { float4 v; asm volatile("ld.shared.v4.f32 {%0,%1,%2,%3}, [%4];" : "=f"(v.x), "=f"(v.y), "=f"(v.z), "=f"(v.w) : "r"(a)); return v; }
__device__ __forceinline__ float2 lds64f(uint32_t a) { float2 v; asm volatile("ld.shared.v2.f32 {%0,%1}, [%2];" : "=f"(v.x), "=f"(v.y) : "r"(a)); return v; }
__device__ __forceinline__ uint4 lds128(uint32_t a) { uint4 v; asm volatile("ld.shared.v4.u32 {%0,%1,%2,%3}, [%4];" : "=r"(v.x), "=r"(v.y), "=r"(v.z), "=r"(v.w) : "r"(a)); return v; }
__device__ __forceinline__ uint32_t lds32(uint32_t a) { uint32_t v; asm volatile("ld.shared.u32 %0, [%1];" : "=r"(v) : "r"(a)); return v; }
__device__ __forceinline__ uint32_t ldbf(const bf16* p) { uint32_t v; asm volatile("ld.global.nc.u16 %0, [%1];" : "=r"(v) : "l"(p)); return v; }
__device__ __forceinline__ void spin_clks(uint32_t n) {
  asm volatile("{ .reg .u32 a, b; .reg .pred p; mov.u32 a, %%clock;\nL: mov.u32 b, %%clock; sub.u32 b, b, a; setp.lt.u32 p, b, %0; @p bra L; }" ::"r"(n) : "memory");
}
__device__ __forceinline__ uint32_t gtime32() { uint32_t t; asm volatile("mov.u32 %0, %%globaltimer_lo;" : "=r"(t)::"memory"); return t; }
__device__ __forceinline__ uint32_t get_tag(uint32_t misc) { mbar_wait(misc + B_TAG, 0); return lds32(misc + MS_TAG); }

template<int TA,int TB> __device__ __forceinline__ void wgmma_ss_n128(float (&d)[64], uint64_t da, uint64_t db, int sc){
  asm volatile("{ .reg .pred p; setp.ne.b32 p, %66, 0;\n wgmma.mma_async.sync.aligned.m64n128k16.f32.bf16.bf16 "
  "{%0,%1,%2,%3,%4,%5,%6,%7,%8,%9,%10,%11,%12,%13,%14,%15,%16,%17,%18,%19,%20,%21,%22,%23,%24,%25,%26,%27,%28,%29,%30,%31,%32,%33,%34,%35,%36,%37,%38,%39,%40,%41,%42,%43,%44,%45,%46,%47,%48,%49,%50,%51,%52,%53,%54,%55,%56,%57,%58,%59,%60,%61,%62,%63}, %64, %65, p, 1, 1, %67, %68; }"
  : "+f"(d[0]),"+f"(d[1]),"+f"(d[2]),"+f"(d[3]),"+f"(d[4]),"+f"(d[5]),"+f"(d[6]),"+f"(d[7]),"+f"(d[8]),"+f"(d[9]),"+f"(d[10]),"+f"(d[11]),"+f"(d[12]),"+f"(d[13]),"+f"(d[14]),"+f"(d[15]),"+f"(d[16]),"+f"(d[17]),"+f"(d[18]),"+f"(d[19]),"+f"(d[20]),"+f"(d[21]),"+f"(d[22]),"+f"(d[23]),"+f"(d[24]),"+f"(d[25]),"+f"(d[26]),"+f"(d[27]),"+f"(d[28]),"+f"(d[29]),"+f"(d[30]),"+f"(d[31]),"+f"(d[32]),"+f"(d[33]),"+f"(d[34]),"+f"(d[35]),"+f"(d[36]),"+f"(d[37]),"+f"(d[38]),"+f"(d[39]),"+f"(d[40]),"+f"(d[41]),"+f"(d[42]),"+f"(d[43]),"+f"(d[44]),"+f"(d[45]),"+f"(d[46]),"+f"(d[47]),"+f"(d[48]),"+f"(d[49]),"+f"(d[50]),"+f"(d[51]),"+f"(d[52]),"+f"(d[53]),"+f"(d[54]),"+f"(d[55]),"+f"(d[56]),"+f"(d[57]),"+f"(d[58]),"+f"(d[59]),"+f"(d[60]),"+f"(d[61]),"+f"(d[62]),"+f"(d[63])
  : "l"(da),"l"(db),"r"(sc),"n"(TA),"n"(TB)); }
template<int TB> __device__ __forceinline__ void wgmma_rs_n128(float (&d)[64], uint32_t a0,uint32_t a1,uint32_t a2,uint32_t a3, uint64_t db, int sc){
  asm volatile("{ .reg .pred p; setp.ne.b32 p, %69, 0;\n wgmma.mma_async.sync.aligned.m64n128k16.f32.bf16.bf16 "
  "{%0,%1,%2,%3,%4,%5,%6,%7,%8,%9,%10,%11,%12,%13,%14,%15,%16,%17,%18,%19,%20,%21,%22,%23,%24,%25,%26,%27,%28,%29,%30,%31,%32,%33,%34,%35,%36,%37,%38,%39,%40,%41,%42,%43,%44,%45,%46,%47,%48,%49,%50,%51,%52,%53,%54,%55,%56,%57,%58,%59,%60,%61,%62,%63}, {%64,%65,%66,%67}, %68, p, 1, 1, %70; }"
  : "+f"(d[0]),"+f"(d[1]),"+f"(d[2]),"+f"(d[3]),"+f"(d[4]),"+f"(d[5]),"+f"(d[6]),"+f"(d[7]),"+f"(d[8]),"+f"(d[9]),"+f"(d[10]),"+f"(d[11]),"+f"(d[12]),"+f"(d[13]),"+f"(d[14]),"+f"(d[15]),"+f"(d[16]),"+f"(d[17]),"+f"(d[18]),"+f"(d[19]),"+f"(d[20]),"+f"(d[21]),"+f"(d[22]),"+f"(d[23]),"+f"(d[24]),"+f"(d[25]),"+f"(d[26]),"+f"(d[27]),"+f"(d[28]),"+f"(d[29]),"+f"(d[30]),"+f"(d[31]),"+f"(d[32]),"+f"(d[33]),"+f"(d[34]),"+f"(d[35]),"+f"(d[36]),"+f"(d[37]),"+f"(d[38]),"+f"(d[39]),"+f"(d[40]),"+f"(d[41]),"+f"(d[42]),"+f"(d[43]),"+f"(d[44]),"+f"(d[45]),"+f"(d[46]),"+f"(d[47]),"+f"(d[48]),"+f"(d[49]),"+f"(d[50]),"+f"(d[51]),"+f"(d[52]),"+f"(d[53]),"+f"(d[54]),"+f"(d[55]),"+f"(d[56]),"+f"(d[57]),"+f"(d[58]),"+f"(d[59]),"+f"(d[60]),"+f"(d[61]),"+f"(d[62]),"+f"(d[63])
  : "r"(a0),"r"(a1),"r"(a2),"r"(a3),"l"(db),"r"(sc),"n"(TB)); }

struct Cx { float re, im; };
__device__ __forceinline__ Cx cmul(Cx a, Cx b) { return {fmaf(a.re, b.re, -a.im * b.im), fmaf(a.re, b.im, a.im * b.re)}; }
__device__ __forceinline__ Cx cfma(Cx a, Cx b, Cx c) { return {fmaf(a.re, b.re, fmaf(-a.im, b.im, c.re)), fmaf(a.re, b.im, fmaf(a.im, b.re, c.im))}; }
__device__ __forceinline__ Cx csq(Cx a) { return {fmaf(a.re, a.re, -a.im * a.im), 2.f * a.re * a.im}; }

__device__ __forceinline__ void ssm_consts(uint32_t lre, uint32_t lim, uint32_t ldt, Cx& lam, Cx& coef) {
  const float ar = bflo(lre), ai = bflo(lim);
  const float dt = bfround(expf(bflo(ldt)));
  float mag = expf(dt * ar), sn, cs;
  sincospif(dt * ai * 0.3183098861837907f, &sn, &cs);
  lam = {mag * cs, mag * sn};
  const float nr = lam.re - 1.f, inv = rcpf(fmaf(ar, ar, ai * ai));
  coef = {(nr * ar + lam.im * ai) * inv, (lam.im * ar - nr * ai) * inv};
}

__device__ __forceinline__ uint32_t ext_frag(float c, uint32_t b_bf16, int q) {
  const float c1 = c - bfround(c), c2 = c1 - bfround(c1);
  return q == 0 ? pack2(c, c1) : q == 1 ? (pack2(c2, 0.f) | (b_bf16 << 16)) : 0u;
}

__device__ __forceinline__ float mish_l2(float h) {
  constexpr float LN2 = 0.6931471805599453f;
  const float u = ex2f(h) + 1.f;
  return h * fmaf(rcpf(fmaf(u, u, 1.f)), -LN2, 0.5f * LN2);
}
__device__ __forceinline__ void prefetch_l2(const void* p, uint32_t bytes) { asm volatile("cp.async.bulk.prefetch.L2.global [%0], %1;" ::"l"(p), "r"(bytes) : "memory"); }
__device__ __forceinline__ void ldm4(uint32_t (&r)[4], uint32_t a) {
  asm volatile("ldmatrix.sync.aligned.m8n8.x4.shared.b16 {%0,%1,%2,%3}, [%4];" : "=r"(r[0]), "=r"(r[1]), "=r"(r[2]), "=r"(r[3]) : "r"(a));
}

template <bool SWAPB>
__global__ void __launch_bounds__(640, 1)
fused_kernel(const __grid_constant__ Maps maps, const __grid_constant__ Params p) {
  extern __shared__ __align__(1024) uint8_t smem_raw[];
  constexpr uint32_t sm = SM_BASE, misc = sm + SM_MISC;
  const int tid = threadIdx.x, W = __shfl_sync(~0u, tid >> 5, 0), wg = W >> 2, lane = tid & 31;
  const int b = blockIdx.x, role = b & 7, chunk = b >> 3;
  const int th = role & 1, cq = role >> 1;
  const int krot = 2 * cq + 2;
  TS0();
  TS(wg, 23);
  const uint32_t aoff = (th ^ 1) * 8192;

  if (wg < 4) {
    const int g = lane >> 2, q = lane & 3, wi = W & 3;
    float t[64];
    uint32_t tag, a0, a1;
    uint32_t stat_addr = misc + MS_RL + q * 16;
    asm volatile("" : "+r"(stat_addr));
    uint4* const img = g_act + (size_t)chunk * 38 * 1024;
    auto put = [&](uint32_t a, const uint32_t (&r)[4]) {
      asm volatile("stmatrix.sync.aligned.m8n8.x4.shared.b16 [%0], {%1,%2,%3,%4};" ::"r"(a + lane * 16), "r"(r[0]), "r"(r[1]), "r"(r[2]), "r"(r[3]) : "memory");
    };
#define SEND(...) asm volatile("fence.proxy.async.shared::cta;" ::: "memory"); __syncwarp(); if (lane == 0) { __VA_ARGS__; asm volatile("cp.async.bulk.commit_group;" ::: "memory"); } __syncwarp()
#define BULK(DST, SRC, BYTES) asm volatile("cp.async.bulk.global.shared::cta.bulk_group [%0], [%1], " #BYTES ";" ::"l"(DST), "r"(SRC) : "memory")
#define SIGNAL(M, N)                                                                                                         \
  if (lane == 0) {                                                                                                           \
    asm volatile("cp.async.bulk.wait_group 0;" ::: "memory");                                                                \
    asm volatile("red.relaxed.gpu.global.add.u32 [%0], %1;" ::"l"(g_cnt + chunk * 32 + (M)), "r"(N) : "memory");             \
  }                                                                                                                          \
  __syncwarp();                                                                                                              \
  nb_arrive((M) < 3 ? (M) : 14, (M) ? 160 : 288)
    if (wg < 2) {
      const int ch = role * 64 + W * 8 + g;
      const uint32_t lre = ldbf(p.lam_re + ch), lim = ldbf(p.lam_im + ch), ldt = ldbf(p.log_dt + ch);
      asm volatile("setmaxnreg.inc.sync.aligned.u32 112;");
      asm volatile("bar.sync 0, 640;" ::: "memory");
      Cx mu, kap, p0, Wq;
      {
        Cx coef;
        ssm_consts(lre, lim, ldt, mu, coef);
        const float cr = (2.f / LOG2E) * coef.re, ci = (2.f / LOG2E) * coef.im;
        kap = SWAPB ? Cx{-ci, -cr} : Cx{cr, ci};
        if (SWAPB) mu.im = -mu.im;
        p0 = csq(csq(csq(csq(mu))));
        const Cx P4 = csq(csq(csq(csq(csq(p0))))), P8 = csq(P4);
        Wq = cmul((q & 1) ? P4 : Cx{1.f, 0.f}, (q & 2) ? P8 : Cx{1.f, 0.f});
      }
      uint2* const pe = g_E + chunk * 512 + ch - (1 + 4 * q) * 512 + (lre >> 16);
      int n = 0;
      sched_fence();
      TS(wg, 0);
#pragma unroll
      for (int kb = 0; kb < 8; kb++) {
        mbar_wait(misc + B_XFULL + 8 * kb, 0);
        mbar_wait(misc + B_F1 + 8 * (kb % 5), kb / 5);
        if (kb == 0) TS(wg, 1);
        if (tid == 0) TSX(5, 8 + kb);
        const uint64_t da = p.dsw + (uint32_t)(wg * 512 + (kb / 5) * p.zero) + (SM_RING >> 4) + (kb % 5) * 1024, db = p.dsw + (uint32_t)(((kb - krot) & 7) * 1024);
        wg_fence();
#pragma unroll
        for (int kk = 0; kk < 4; kk++) {
          wgmma_ss_n128<0, 0>(t, da + kk * 2, db + kk * 2, (kb | kk) != 0);
          if (kk == 0 && kb > 0) { wg_commit(); wg_wait<1>(); warp_arrive<1>(misc + B_E1 + 8 * ((kb - 1) % 5)); }
        }
        if (kb == 7) {
          mbar_wait(misc + B_STAT, 0);
          const float2 a = lds64f(q < 2 ? sm + SM_S4 + 1024 + (W * 8 + g) * 16 + q * 8 : misc + MS_TAG + 16);
          wg_fence();
          wgmma_rs_n128<0>(t, __float_as_uint(a.x), __float_as_uint(a.y), 0u, 0u, p.dext, 1);
        }
        wg_commit();
      }
      tag = lds32(misc + MS_TAG);
      wg_wait<0>();
      warp_arrive<1>(misc + B_E1 + 16);
      pin(t);
      TS(wg, 2);
      Cx E = {0.f, 0.f}, E2 = {0.f, 0.f};
#pragma unroll
      for (int u = 0; u < 4; u++) {
#pragma unroll
        for (int c = 0; c < 2; c++) {
          const float4 r4 = lds128f(stat_addr + c * 256 + u * 64);
#pragma unroll
          for (int e = 0; e < 4; e++) {
            const int k = 32 * c + 8 * u + 4 * (e >> 1) + (e & 1);
            const float r = e == 0 ? r4.x : e == 1 ? r4.y : e == 2 ? r4.z : r4.w;
            t[k] *= r; t[k + 2] *= r;
            if (c == 0) E = cfma(mu, E, Cx{t[k], t[k + 2]}); else E2 = cfma(mu, E2, Cx{t[k], t[k + 2]});
          }
        }
        if (u == J0POS) { sched_fence(); nb_arrive(NB_JOB, 416); }
      }
      const Cx E1 = E, p1 = csq(p0), p2 = csq(p1);
      E = cfma(p0, E, E2);
      Cx y = {__shfl_up_sync(~0u, E.re, 1, 4), __shfl_up_sync(~0u, E.im, 1, 4)};
      if (q >= 1) E = cfma(p1, y, E);
      y = {__shfl_up_sync(~0u, E.re, 2, 4), __shfl_up_sync(~0u, E.im, 2, 4)};
      if (q >= 2) E = cfma(p2, y, E);
      if (q == 3) st_ll64(pe + 13 * 512, (__float_as_uint(E.re) & ~1u) | tag, __float_as_uint(E.im));
      if (J0POS == 4) nb_arrive(NB_JOB, 416);
      sched_fence();
      TS(wg, 4);
      Cx X = {__shfl_up_sync(~0u, E.re, 1, 4), __shfl_up_sync(~0u, E.im, 1, 4)};
      if (q == 0) X = {0.f, 0.f};
#pragma unroll
      for (int i = 0; i < 32; i++) {
        const int k = (i >> 1) * 4 + (i & 1);
        const float u0 = t[k], u1 = t[k + 2];
        t[k] = fmaf(kap.re, u0, -kap.im * u1); t[k + 2] = fmaf(kap.re, u1, kap.im * u0);
        if (POLITE && (i % POLITE) == POLITE - 1) sched_fence();
      }
      sched_fence();
      TS(wg, 5);
      const int nv = chunk - 4 * q;
      uint2 e[4], e2[4];
#pragma unroll
      for (int d = 0; d < 4; d++) e[d] = e2[d] = make_uint2(tag, 0u);
      auto poll = [&](uint2 (&e)[4]) {
#pragma unroll
        for (int d = 0; d < 4; d++)
          asm volatile("{ .reg .pred p; .reg .b64 u; setp.gt.s32 p, %3, %4; mov.b64 u, {%0,%1}; @p ld.relaxed.gpu.global.b64 u, [%2]; mov.b64 {%0,%1}, u; }"
                       : "+r"(e[d].x), "+r"(e[d].y) : "l"(pe - d * 512), "r"(nv), "r"(d) : "memory");
      };
      if (CPOLL) __nanosleep(CPOLL);
      poll(e);
      Cx H = cmul(kap, X), H2 = cmul(kap, cfma(p0, X, E1));
      const Cx F = cmul(kap, cmul((q & 1) ? p1 : Cx{1.f, 0.f}, (q & 2) ? p2 : Cx{1.f, 0.f})), F2 = cmul(F, p0);
      const Cx P = csq(p2), W2 = cmul(Wq, csq(P));
      nb_sync(NB_STG, 384);
#define STALE(e) __any_sync(~0u, (((e[0].x ^ tag) | (e[1].x ^ tag) | (e[2].x ^ tag) | (e[3].x ^ tag)) & 1) != 0)
      while (STALE(e)) { poll(e); if (++n > SPIN_LIMIT) __trap(); }
      TS(wg, 3);
      {
        const Cx A0 = cfma(P, Cx{__uint_as_float(e[1].x), __uint_as_float(e[1].y)}, Cx{__uint_as_float(e[0].x), __uint_as_float(e[0].y)});
        const Cx A1 = cfma(P, Cx{__uint_as_float(e[3].x), __uint_as_float(e[3].y)}, Cx{__uint_as_float(e[2].x), __uint_as_float(e[2].y)});
        Cx A = cfma(W2, A1, cmul(Wq, A0));
        A.re += __shfl_xor_sync(~0u, A.re, 1); A.im += __shfl_xor_sync(~0u, A.im, 1);
        A.re += __shfl_xor_sync(~0u, A.re, 2); A.im += __shfl_xor_sync(~0u, A.im, 2);
        H = cfma(F, A, H); H2 = cfma(F2, A, H2);
      }
      TS(wg, 6);
      const uint32_t hs = sm + SM_S4 + W * 4096;
      uint4* const hd = img + 2 * role * 1024 + W * 64;
#pragma unroll
      for (int i = 0; i < 2; i++) {
        uint32_t hr[4], hi[4], gr[4], gi[4];
#pragma unroll
        for (int jj = 0; jj < 4; jj++) {
          const int j = 4 * i + jj;
          const Cx h0 = cfma(mu, H, Cx{t[4 * j], t[4 * j + 2]}), g0 = cfma(mu, H2, Cx{t[32 + 4 * j], t[34 + 4 * j]});
          H = cfma(mu, h0, Cx{t[4 * j + 1], t[4 * j + 3]}); H2 = cfma(mu, g0, Cx{t[33 + 4 * j], t[35 + 4 * j]});
          hr[jj] = pack2(h0.re, H.re); gr[jj] = pack2(g0.re, H2.re);
          hi[jj] = SWAPB ? pack2(h0.im, H.im) : pack2(-h0.im, -H.im); gi[jj] = SWAPB ? pack2(g0.im, H2.im) : pack2(-g0.im, -H2.im);
        }
        if (i == 1 && HSPLIT) { sched_fence(); SEND(BULK(hd, hs, 512); BULK(hd + 512, hs + 1024, 512); BULK(hd + 1024, hs + 2048, 512); BULK(hd + 1536, hs + 3072, 512)); }
        put(hs + i * 512, hr); put(hs + 1024 + i * 512, gr);
        put(hs + 2048 + i * 512, hi); put(hs + 3072 + i * 512, gi);
        if (i == J1POS) nb_arrive(NB_JOB + 1, J1N);
        sched_fence();
      }
      if (HSPLIT) { SEND(BULK(hd + 32, hs + 512, 512); BULK(hd + 544, hs + 1536, 512); BULK(hd + 1056, hs + 2560, 512); BULK(hd + 1568, hs + 3584, 512)); }
      else { SEND(BULK(hd, hs, 1024); BULK(hd + 512, hs + 1024, 1024); BULK(hd + 1024, hs + 2048, 1024); BULK(hd + 1536, hs + 3072, 1024)); }
      if (J1POS == 4) nb_arrive(NB_JOB + 1, J1N);
      TS(wg, 7);
      SIGNAL(0, 1);
      if (wg == 1) { nb_arrive(NB_STG + 1, 256); nb_arrive(NB_STG + 2, 256); }
      TS(wg, 18);
    } else {
      asm volatile("setmaxnreg.inc.sync.aligned.u32 112;");
      asm volatile("bar.sync 0, 640;" ::: "memory");
      const int ht = tid & 127;
      if (wg == 3) {
        const int pos = 16 * role + (ht >> 3);
        const int f0 = min(((ht & 64) / 4 + role) * 64 + (ht & 63), 1375), f1 = (8 + role) * 64 + wi * 16 + (lane & 15);
        const uint32_t bb0 = ldbf(p.b1 + f0), bb1 = ldbf(p.b1 + f1);
        float sa[4] = {0.f, 0.f, 0.f, 0.f}, sq[4] = {0.f, 0.f, 0.f, 0.f};
        tag = get_tag(misc);
#pragma unroll 1
        for (int kb = 0; kb < 8; kb += 2) {
          mbar_wait(misc + B_XFULL + 8 * kb, 0);
          mbar_wait(misc + B_XFULL + 8 * kb + 8, 0);
          const uint32_t a = sm + ((kb - krot) & 7) * 16384 + pos * 128 + (ht & 7) * 16;
          const uint4 u = lds128(a), v = lds128(a + 16384);
          const uint32_t w[8] = {u.x, u.y, u.z, u.w, v.x, v.y, v.z, v.w};
#pragma unroll
          for (int i = 0; i < 8; i++) {
            const float d0 = bflo(w[i]), d1 = bfhi(w[i]);
            sa[(2 * i) & 3] += d0; sa[(2 * i + 1) & 3] += d1;
            sq[(2 * i) & 3] = fmaf(d0, d0, sq[(2 * i) & 3]); sq[(2 * i + 1) & 3] = fmaf(d1, d1, sq[(2 * i + 1) & 3]);
          }
        }
        TS(2, 1);
        float m0 = (sa[0] + sa[1]) + (sa[2] + sa[3]), q0 = (sq[0] + sq[1]) + (sq[2] + sq[3]);
#pragma unroll
        for (int o = 1; o < 8; o <<= 1) { m0 += __shfl_xor_sync(~0u, m0, o); q0 += __shfl_xor_sync(~0u, q0, o); }
        const float md = m0 * (1.f / 512.f);
        const float var = fmaxf(fmaf(-md, md, q0 * (1.f / 512.f)), 0.f);
        float sd;
        asm("sqrt.approx.f32 %0, %1;" : "=f"(sd) : "f"(bfround(bfround(var) + 1e-5f)));
        if ((lane & 7) == 0) st_ll64(g_st + chunk * 128 + pos, (__float_as_uint(LOG2E * rcpf(bfround(sd))) & ~1u) | tag, pack2(-md, sd));
        TS(2, 0);
        uint32_t cs[8];
        int n = 0;
        mbar_wait(misc + B_STAT, 0);
        do {
#pragma unroll
          for (int u = 0; u < 8; u++) cs[u] = ld_ll32(g_cs + (u >> 1) * 1536 + ((u & 1) ? f1 : f0));
          if (++n > SPIN_LIMIT) __trap();
        } while (__any_sync(~0u, (((cs[0] ^ tag) | (cs[1] ^ tag) | (cs[2] ^ tag) | (cs[3] ^ tag) | (cs[4] ^ tag) | (cs[5] ^ tag) | (cs[6] ^ tag) | (cs[7] ^ tag)) & 1) != 0));
        const float c0 = (__uint_as_float(cs[0]) + __uint_as_float(cs[2])) + (__uint_as_float(cs[4]) + __uint_as_float(cs[6]));
        const float c1 = (__uint_as_float(cs[1]) + __uint_as_float(cs[3])) + (__uint_as_float(cs[5]) + __uint_as_float(cs[7]));
        asm volatile("st.shared.v2.u32 [%0], {%1,%2};" ::"r"(misc + MS_EXT + ht * 16 + 8), "r"(ext_frag(c0, bb0, 0)), "r"(ext_frag(c0, bb0, 1)) : "memory");
        mbar_arrive(misc + B_GO);
        const uint32_t w = ext_frag(c1, bb1, lane >> 4);
        a0 = __shfl_sync(~0u, w, (q & 1) * 16 + g); a1 = __shfl_sync(~0u, w, (q & 1) * 16 + g + 8);
        if (q >= 2) a0 = a1 = 0;
      } else {
        const int chs = role * 64 + chunk * 4 + wi;
        const uint4* src = reinterpret_cast<const uint4*>(((lane & 16) ? p.b_hi : p.b_lo) + (size_t)chs * 512) + (lane & 15);
        uint4 vb[4];
#pragma unroll
        for (int i = 0; i < 4; i++) {
          spin_clks(HEARLY);
          asm volatile("ld.global.nc.v4.u32 {%0,%1,%2,%3}, [%4];" : "=r"(vb[i].x), "=r"(vb[i].y), "=r"(vb[i].z), "=r"(vb[i].w) : "l"(src + 16 * i));
        }
        tag = get_tag(misc);
        float s0 = 0.f, s1 = 0.f;
#pragma unroll
        for (int i = 0; i < 4; i++) {
          const uint4 v = vb[i];
          s0 += bflo(v.x); s1 += bfhi(v.x); s0 += bflo(v.y); s1 += bfhi(v.y);
          s0 += bflo(v.z); s1 += bfhi(v.z); s0 += bflo(v.w); s1 += bfhi(v.w);
        }
        s0 += s1;
#pragma unroll
        for (int o = 1; o < 16; o <<= 1) s0 += __shfl_xor_sync(~0u, s0, o);
        s1 = __shfl_down_sync(~0u, s0, 16);
        if (lane == 0) st_ll64(g_rs + chs, (__float_as_uint(s0) & ~1u) | tag, __float_as_uint(s1));
        TS(3, 0);
        if (chunk < 12) {
          float s[8];
#pragma unroll
          for (int i = 0; i < 8; i++) s[i] = 0.f;
          mbar_wait(misc + B_CS, 0);
          TS(3, 2);
#pragma unroll 2
          for (int i = 0; i < 8; i++) {
            const uint4 v = lds128(sm + SM_STG + i * 2048 + (ht >> 3) * 128 + (((ht ^ (ht >> 3)) & 7) << 4));
            s[0] += bflo(v.x); s[1] += bfhi(v.x); s[2] += bflo(v.y); s[3] += bfhi(v.y);
            s[4] += bflo(v.z); s[5] += bfhi(v.z); s[6] += bflo(v.w); s[7] += bfhi(v.w);
          }
#pragma unroll
          for (int i = 0; i < 4; i++) { const bool up = lane & 16; float v = __shfl_xor_sync(~0u, up ? s[i] : s[i + 4], 16); s[i] = (up ? s[i + 4] : s[i]) + v; }
#pragma unroll
          for (int i = 0; i < 2; i++) { const bool up = lane & 8; float v = __shfl_xor_sync(~0u, up ? s[i] : s[i + 2], 8); s[i] = (up ? s[i + 2] : s[i]) + v; }
          asm volatile("bar.sync 1, 128;" ::: "memory");
          asm volatile("st.shared.v2.f32 [%0], {%1,%2};" ::"r"(sm + SM_STG + wi * 256 + (lane & 7) * 32 + (lane >> 3) * 8), "f"(s[0]), "f"(s[1]) : "memory");
          asm volatile("bar.sync 1, 128;" ::: "memory");
          if (ht < 64) {
            float v = 0.f;
#pragma unroll
            for (int i = 0; i < 4; i++) v += __uint_as_float(lds32(sm + SM_STG + i * 256 + ht * 4));
            st_ll32(g_cs + (chunk & 3) * 1536 + ((chunk >> 2) * 8 + role) * 64 + ht, (__float_as_uint(v) & ~1u) | tag);
          }
          __syncwarp();
        }
        nb_arrive(NB_STG, 384);
        TS(3, 1);
      }
    }
    if (wg != 1) {
      const int m = wg == 0 ? 2 : wg - 2, tile = 8 * m + role;
      TS(wg, 8);
      sched_fence();
      nb_sync(NB_JOB + m, m == 0 ? 416 : m == 1 ? J1N : 320);
      const uint32_t rel = m == 2 ? 1 : 2;
#pragma unroll
      for (int i = 0; i < 4; i++) {
        mbar_wait(misc + B_F1 + 8 * ((i + 3) & 3), (m + (i == 0)) & 1);
        if (i == 3 && m != 1) {
          mbar_wait(misc + B_GO, 0);
          const uint32_t fa = q < 2 ? misc + MS_EXT + (m * 32 + wi * 16 + g) * 16 + 8 + q * 4 : misc + MS_TAG + 16;
          a0 = lds32(fa); a1 = lds32(q < 2 ? fa + 128 : fa);
        }
        wg_fence();
#pragma unroll
        for (int kk = 0; kk < 8; kk++) {
          wgmma_ss_n128<1, 0>(t, p.dsw + (SM_RING >> 4) + ((i + 3) & 3) * 1024 + kk * 128, p.dsw + i * 2048 + (kk >> 2) * 1024 + (kk & 3) * 2, (i | kk) != 0);
          if (kk == 1 && i > 0) { wg_commit(); wg_wait<1>(); warp_arrive_n(m == 2 ? misc + B_EMPTY + 16 * (i - 1) + 8 : misc + B_E1 + 8 * ((i + 2) & 3), rel); }
          if (kk == 3) wg_commit();
          if (kk == 5) { wg_commit(); wg_wait<1>(); warp_arrive_if<1>(misc + B_EMPTY + 16 * i, m == 2); }
          if (kk == 5 && i == 3) nb_arrive(NB_JOB + m + 1, m == 0 ? J1N : m == 1 ? 320 : 256);
        }
        if (i == 3) { wg_fence(); wgmma_rs_n128<0>(t, a0, a1, 0u, 0u, p.dext, 1); }
        wg_commit();
      }
      wg_wait<0>();
      warp_arrive_n(m == 2 ? misc + B_EMPTY + 56 : misc + B_E1 + 16, rel);
      pin(t);
      TS(wg, 9);
      if (tile * 64 + wi * 16 < 1376) {
        if ((MHOLD >> m) & 1) nb_sync(NB_STG + 1 + m, 256);
        TS(wg, 10);
        const uint32_t as = sm + SM_STG + (W & 7) * 2048;
        uint4* const ad = img + (16 + tile) * 1024 + wi * 128;
        float4 sv[2];
        uint32_t r0[4], r1[4], k0[4], k1[4];
        sv[0] = lds128f(stat_addr); sv[1] = lds128f(stat_addr + 64);
#pragma unroll
        for (int i = 0; i < 4; i++) {
#pragma unroll
          for (int u = 0; u < 2; u++) {
            const int k = 16 * i + 8 * u;
            t[k] *= sv[u].x; t[k + 1] *= sv[u].y; t[k + 2] *= sv[u].x; t[k + 3] *= sv[u].y;
            t[k + 4] *= sv[u].z; t[k + 5] *= sv[u].w; t[k + 6] *= sv[u].z; t[k + 7] *= sv[u].w;
            if (i < 3) sv[u] = lds128f(stat_addr + (2 * i + 2 + u) * 64);
          }
          sched_fence();
#pragma unroll
          for (int jj = 0; jj < 4; jj++) {
            const int j = 4 * i + jj;
            r0[jj] = pack2(mish_l2(t[4 * j]), mish_l2(t[4 * j + 1]));
            r1[jj] = pack2(mish_l2(t[4 * j + 2]), mish_l2(t[4 * j + 3]));
          }
          if (i & 1) {
            sched_fence();
            if (i == 1) { if (!((MHOLD >> m) & 1)) nb_sync(NB_STG + 1 + m, 256); }
            else { if (lane == 0) asm volatile("cp.async.bulk.wait_group.read 0;" ::: "memory"); __syncwarp(); }
            put(as, k0); put(as + 1024, k1); put(as + 512, r0); put(as + 1536, r1);
          } else {
#pragma unroll
            for (int jj = 0; jj < 4; jj++) { k0[jj] = r0[jj]; k1[jj] = r1[jj]; }
          }
          if (i == 2) { sched_fence(); SEND(BULK(ad, as, 2048)); }
        }
        SEND(BULK(ad + 512, as, 2048));
      } else {
        nb_arrive(NB_STG + 3, 256);
      }
      TS(wg, 11);
      SIGNAL(m + 1, 2);
      if (m == 0) nb_arrive(NB_STG + 3, 256);
      TS(wg, 19);
    }
    if (wg != 0) {
      const int pl = th * 64 + wi * 16;
      const uint32_t xa = sm + 6 * 16384 + (pl + (lane & 15)) * 128 + (((lane >> 4) ^ (lane & 7)) << 4);
      if (wg < 3) nb_sync(NB_JOB + wg + 2, 256);
      TS(wg, 12);
      if (wg == 1) {
#pragma unroll 1
        for (int r = 0; r < 2; r++) {
          const uint64_t da0 = p.dns + (uint32_t)(r * p.zero), da1 = da0 + (aoff >> 4), db0 = p.dsw + (uint32_t)(r * p.zero);
#pragma unroll
          for (int i = 0; i < 8; i++) {
            mbar_wait(misc + B_FULL + 8 * i, r);
            if (i == 0) TS(wg, 13 + 3 * r);
            if (i == 7 && r == 1) nb_arrive(NB_JOB + 4, 256);
            wg_fence();
#pragma unroll
            for (int kk = 0; kk < 4; kk++) {
              wgmma_ss_n128<1, 0>(t, (i < 6 ? da0 : da1) + (slotA(i) >> 4) + kk * 128, db0 + (slotB(i) >> 4) + kk * 2, (r | i | kk) != 0);
              if (kk == RELK) { wg_commit(); wg_wait<1>(); if (i > 0) warp_arrive<1>(misc + B_EMPTY + 8 * i - 8); else warp_arrive_if<1>(misc + B_EMPTY + 56, r > 0); }
            }
            if (RELK < 3) wg_commit();
          }
        }
        wg_wait<0>();
        warp_arrive<1>(misc + B_EMPTY + 56);
      } else if (wg == 2) {
#pragma unroll 1
        for (int r = 0; r < 3; r++) {
          const uint64_t da0 = p.dns + (uint32_t)(r * p.zero), da1 = da0 + (aoff >> 4), db0 = p.dsw8k + (uint32_t)(r * p.zero);
#pragma unroll
          for (int i = 0; i < 8; i++) {
            mbar_wait(misc + B_FULL + 8 * i, r & 1);
            if (i == 0) TS(wg, 16 + r);
            if (i == 0 && r == 2) nb_arrive(NB_FREE, 256);
            wg_fence();
#pragma unroll
            for (int kk = 0; kk < 4; kk++) {
              wgmma_ss_n128<1, 1>(t, (i < 6 ? da0 : da1) + (slotA(i) >> 4) + kk * 128, db0 + (slotB(i) >> 4) + kk * 128, (r | i | kk) != 0);
              if (kk == 1 && i == 5) { if (r == 2) goto a_done; wg_fence(); }
              if (kk == RELK) { wg_commit(); wg_wait<1>(); if (i > 0) warp_arrive<1>(misc + B_EMPTY + 8 * i - 8); else warp_arrive_if<1>(misc + B_EMPTY + 56, r > 0); }
            }
            if (RELK < 3) wg_commit();
          }
        }
      a_done:
        wg_commit();
        wg_wait<0>();
      }
      pin(t);
      TS(wg, 14);
      const uint32_t exs = sm + slotB(6) + (tid & 127) * 16;
      if (wg == 2) {
#pragma unroll
        for (int j = 0; j < 8; j++) {
          asm volatile("st.shared.v4.u32 [%0], {%1,%2,%3,%4};" ::"r"(exs + 16384 + j * 2048), "r"(pack2(t[8 * j], t[8 * j + 1])), "r"(pack2(t[8 * j + 2], t[8 * j + 3])),
                       "r"(pack2(t[8 * j + 4], t[8 * j + 5])), "r"(pack2(t[8 * j + 6], t[8 * j + 7])) : "memory");
          if ((j & 3) == 3) { nb_arrive(j < 4 ? 3 : NB_JOB, 256); sched_fence(); }
        }
      } else {
      uint32_t dv[8];
#pragma unroll
      for (int j = 0; j < 8; j++) asm volatile("ld.global.nc.u32 %0, [%1];" : "=r"(dv[j]) : "l"(p.dskip + cq * 128 + (wg >> 1) * 64 + 8 * j + 2 * q));
      float xf[32];
      if (wg == 1) {
        nb_sync(NB_FREE, 256);
#pragma unroll
        for (int j = 0; j < 8; j++)
          asm volatile("st.shared.v4.f32 [%0], {%1,%2,%3,%4};" ::"r"(exs + j * 2048), "f"(t[32 + 4 * j]), "f"(t[33 + 4 * j]), "f"(t[34 + 4 * j]), "f"(t[35 + 4 * j]) : "memory");
        nb_arrive(9, 256);
        TS(wg, 15);
      } else {
        mbar_wait(misc + B_RDY + 24, 0);
#pragma unroll
        for (int i = 0; i < 32; i++) t[i] = 0.f;
      }
      {
        const uint32_t e0 = lds32(misc + MS_EXT + (pl + g) * 16 + 4), e1 = lds32(misc + MS_EXT + (pl + g + 8) * 16 + 4);
        const float r0 = rcpf(bfhi(e0)), r1 = rcpf(bfhi(e1)), nr0 = r0 * bflo(e0), nr1 = r1 * bflo(e1);
#pragma unroll
        for (int i = 0; i < 4; i++) {
          uint32_t xr[4];
          ldm4(xr, (xa ^ (i * 32)) + (wg >> 1) * 16384);
#pragma unroll
          for (int u = 0; u < 2; u++) {
            const int k = 8 * i + 4 * u;
            const float d0 = bflo(dv[2 * i + u]), d1 = bfhi(dv[2 * i + u]);
            xf[k] = bflo(xr[2 * u]); xf[k + 1] = bfhi(xr[2 * u]); xf[k + 2] = bflo(xr[2 * u + 1]); xf[k + 3] = bfhi(xr[2 * u + 1]);
            t[k] = fmaf(fmaf(xf[k], r0, nr0), d0, t[k]); t[k + 1] = fmaf(fmaf(xf[k + 1], r0, nr0), d1, t[k + 1]);
            t[k + 2] = fmaf(fmaf(xf[k + 2], r1, nr1), d0, t[k + 2]); t[k + 3] = fmaf(fmaf(xf[k + 3], r1, nr1), d1, t[k + 3]);
          }
        }
      }
#pragma unroll 1
      for (int real = (WARM && wg == 3) ? 0 : 1; real < 2; real++) {
        if (wg == 3 && real) {
          nb_sync(9, 256);
#pragma unroll
          for (int j = 0; j < 8; j++) { const float4 v = lds128f(exs + j * 2048); t[4 * j] += v.x; t[4 * j + 1] += v.y; t[4 * j + 2] += v.z; t[4 * j + 3] += v.w; }
        }
        sched_fence();
        if (real) nb_sync(wg == 1 ? 3 : NB_JOB, 256);
        uint4 gv[4];
#pragma unroll
        for (int j = 0; j < 4; j++) gv[j] = lds128(exs + 16384 + (wg >> 1) * 8192 + j * 2048);
        const uint32_t ob = sm + slotB(1) + (wg >> 1) * 16384 + wi * 4096, oa = ob + g * 256 + (((q >> 1) ^ (2 * g & 7)) << 4) + (q & 1) * 8;
#pragma unroll
        for (int j = 0; j < 8; j++) {
          const uint32_t w0 = (j & 1) ? gv[j >> 1].z : gv[j >> 1].x, w1 = (j & 1) ? gv[j >> 1].w : gv[j >> 1].y;
          const float hv[4] = {bflo(w0), bfhi(w0), bflo(w1), bfhi(w1)};
          float o[4];
#pragma unroll
          for (int i = 0; i < 4; i++) o[i] = fmaf(t[4 * j + i], fmaf(hv[i], tanhf_hw(hv[i]), hv[i]), xf[4 * j + i]);
          asm volatile("{ .reg .pred p; setp.ne.u32 p, %6, 0; @p st.shared.v2.f32 [%0], {%2,%3}; @p st.shared.v2.f32 [%1], {%4,%5}; }"
                       ::"r"((oa ^ ((j & 3) * 32)) + (j >> 2) * 2048), "r"((oa ^ ((j & 3) * 32 + 16)) + (j >> 2) * 2048 + 128), "f"(o[0]), "f"(o[1]), "f"(o[2]), "f"(o[3]), "r"(real) : "memory");
          if ((j & 3) == 3) {
            SEND(if (real) asm volatile("cp.async.bulk.tensor.5d.global.shared::cta.bulk_group [%0, {%2,%4,%3,%3,%5}], [%1];" ::"l"(&maps.out), "r"(ob + (j >> 2) * 2048),
                              "r"(cq * 128 + (wg >> 1) * 64 + (j >> 2) * 32), "r"(0), "r"(pl >> 3), "r"(chunk) : "memory"));
            TS(wg, 20 + (j >> 2));
            sched_fence();
          }
        }
      }
      if (lane == 0) asm volatile("cp.async.bulk.wait_group.read 0;" ::: "memory");
      }
    }
    TSW(wg);
  } else {
    asm volatile("setmaxnreg.dec.sync.aligned.u32 32;");
    auto load_x = [&](int kb) {
      mbar_expect(misc + B_XFULL + 8 * kb, 16384);
      asm volatile("cp.async.bulk.tensor.5d.shared::cluster.global.mbarrier::complete_tx::bytes [%0], [%1, {%3,%4,%4,%4,%5}], [%2];" ::"r"(sm + ((kb - krot) & 7) * 16384),
                   "l"(&maps.x), "r"(misc + B_XFULL + 8 * kb), "r"(kb * 64), "r"(0), "r"(chunk) : "memory");
    };
    auto load_b = [&](int i) {
      const uint32_t s = i < 5 ? i : i - 5, full = misc + B_F1 + 8 * s;
      mbar_expect(full, 16384);
      asm volatile("cp.async.bulk.tensor.4d.shared::cluster.global.mbarrier::complete_tx::bytes [%0], [%1, {%3,%4,%4,%5}], [%2];" ::"r"(sm + SM_RING + s * 16384),
                   "l"(&maps.b), "r"(full), "r"(i * 64), "r"(0), "r"(role * 8) : "memory");
    };
    if (elect_one()) {
      if (W == 16) {
        for (int i = 0; i < 8; i++) mbar_init(misc + B_XFULL + 8 * i, 1);
        mbar_init(misc + B_CS, 1);
        load_x(0);
      } else if (W == 17) {
        for (int i = 0; i < 5; i++) mbar_init(misc + B_F1 + 8 * i, 1);
        load_b(0);
      } else if (W == 18) {
        for (int i = 0; i < 5; i++) mbar_init(misc + B_E1 + 8 * i, 8);
        for (int i = 0; i < 5; i++) mbar_init(misc + B_RDY + 8 * i, 1);
        mbar_init(misc + B_GO, 128);
      } else {
        mbar_init(misc + B_STAT, 64);
        for (int i = 0; i < 8; i++) { mbar_init(misc + B_FULL + 8 * i, 1); mbar_init(misc + B_EMPTY + 8 * i, 4); }
      }
    }
    __syncwarp();
    asm volatile("bar.arrive 0, 640;" ::: "memory");
    if (W >= 18) { asm volatile("bar.arrive 9, 96;" ::: "memory"); asm volatile("bar.sync 2, 64;" ::: "memory"); }
    if (W == 16) {
      if (elect_one()) {
#pragma unroll 1
        for (int kb = 1; kb < 8; kb++) { if (PACE) spin_clks(PACE); load_x(kb); }
        if (chunk < 12) {
          if (CSTRIG >= 0) mbar_wait(misc + B_XFULL + 8 * CSTRIG, 0);
          mbar_expect(misc + B_CS, 16384);
          asm volatile("cp.async.bulk.tensor.2d.shared::cluster.global.mbarrier::complete_tx::bytes [%0], [%1, {%3,%4}], [%2];" ::"r"(sm + SM_STG),
                       "l"(&maps.w1), "r"(misc + B_CS), "r"(((chunk >> 2) * 8 + role) * 64), "r"((chunk & 3) * 128) : "memory");
        }
        TSX(4, 0);
      }
      __syncwarp();
      nb_sync(NB_JOB + 2, 320);
    } else if (W == 17) {
      if (elect_one()) {
#pragma unroll 1
        for (int i = 1; i < 5; i++) { if (PACEB) spin_clks(PACEB); load_b(i); }
      }
      __syncwarp();
      asm volatile("bar.sync 9, 96;" ::: "memory");
      if (elect_one()) {
#pragma unroll 1
        for (int i = 5; i < 8; i++) { mbar_wait(misc + B_E1 + 8 * (i - 5), 0); load_b(i); }
        TSX(4, 1);
#pragma unroll 1
        for (int i = 0; i < 12; i++) {
          const uint32_t s = (i + 3) & 3, full = misc + B_F1 + 8 * s;
          mbar_wait(misc + B_E1 + 8 * s, ((i + 3) >> 2) & 1);
          mbar_expect(full, 16384);
          asm volatile("cp.async.bulk.tensor.2d.shared::cluster.global.mbarrier::complete_tx::bytes [%0], [%1, {%3,%4}], [%2];" ::"r"(sm + SM_RING + s * 16384),
                       "l"(&maps.w1), "r"(full), "r"(((i >> 2) * 8 + role) * 64), "r"(((2 * i + krot) & 7) * 64) : "memory");
        }
      }
    } else if (W == 18) {
      if (lane < 5) asm volatile("prefetch.tensormap [%0];" ::"l"(reinterpret_cast<const CUtensorMap*>(&maps) + 2 + lane) : "memory");
      {
        const uint32_t tag = get_tag(misc);
        uint2 v0, v1;
        int c = 0;
        do {
          v0 = ld_ll64(g_rs + role * 64 + lane); v1 = ld_ll64(g_rs + role * 64 + 32 + lane);
          if (++c > SPIN_LIMIT) __trap();
        } while (__any_sync(~0u, (((v0.x ^ tag) | (v1.x ^ tag)) & 1) != 0));
        mbar_wait(misc + B_E1 + 32, 0);
#pragma unroll 1
        for (int i = 0; i < 2; i++) {
          const float x = __uint_as_float(v0.x), y = __uint_as_float(v0.y);
          asm volatile("st.shared.v4.u32 [%0], {%1,%2,%3,%4};" ::"r"(sm + SM_S4 + 1024 + (i * 32 + lane) * 16), "r"(ext_frag(x, 0, 0)), "r"(ext_frag(y, 0, 0)),
                       "r"(ext_frag(x, 0, 1)), "r"(ext_frag(y, 0, 1)) : "memory");
          v0 = v1;
        }
        mbar_arrive(misc + B_STAT);
        if (lane == 0) TSX(4, 7);
      }
      __syncwarp();
      nb_sync(NB_JOB, 416);
      if (lane == 0) {
        const unsigned long long target = (unsigned long long)lds32(misc + MS_TAG + 8) * 128;
        unsigned long long now, a, c;
        asm volatile("mov.u64 %0, %%globaltimer;" : "=l"(now)::"memory");
        asm volatile("red.relaxed.gpu.global.max.u64 [%0], %1;" ::"l"(&g_go.x), "l"(now) : "memory");
        asm volatile("red.relaxed.gpu.global.add.u64 [%0], 1;" ::"l"(&g_go.y) : "memory");
        TSX(4, 5);
        prefetch_l2(reinterpret_cast<const char*>(p.c_re) + b * 4096, 4096);
        prefetch_l2(reinterpret_cast<const char*>(p.c_im) + b * 4096, 4096);
        prefetch_l2(reinterpret_cast<const char*>(p.w2) + b * 11008, 11008);
        int n = 0;
        do {
          __nanosleep(300);
          asm volatile("ld.relaxed.gpu.global.v2.u64 {%0,%1}, [%2];" : "=l"(a), "=l"(c) : "l"(&g_go) : "memory");
          if (++n > SPIN_LIMIT) __trap();
        } while (c < target);
        TSX(4, 4);
        int left;
        while ((left = (int)((uint32_t)a + GONS - gtime32())) > 0 && left <= GONS) __nanosleep(left > 200 ? left >> 1 : 0);
        TSX(4, 6);
      }
      __syncwarp();
      nb_arrive(NB_JOB + 2, 320);
    } else {
      const uint32_t e = ld_ll32(g_epoch + b) + 1, tag = e & 1;
      __syncwarp();
      if (lane == 0) {
        if ((uint32_t)__cvta_generic_to_shared(smem_raw) != SM_BASE) __trap();
        g_epoch[b] = e;
        asm volatile("st.shared.v4.u32 [%0], {%1,%2,%3,%2};" ::"r"(misc + MS_TAG), "r"(tag), "r"(0), "r"(e) : "memory");
        asm volatile("st.shared.v2.u32 [%0], {%1,%1};" ::"r"(misc + MS_TAG + 16), "r"(0) : "memory");
        mbar_arrive(misc + B_TAG);
        TSX(4, 2);
      }
      st_ll64(g_E + chunk * 512 + role * 64 + lane, tag ^ 1, 0u);
      st_ll64(g_E + chunk * 512 + role * 64 + 32 + lane, tag ^ 1, 0u);
      uint2 v[4];
      int c = 0;
      while (true) {
#pragma unroll
        for (int i = 0; i < 4; i++) v[i] = ld_ll64(g_st + chunk * 128 + i * 32 + lane);
        if (!__any_sync(~0u, (((v[0].x ^ tag) | (v[1].x ^ tag) | (v[2].x ^ tag) | (v[3].x ^ tag)) & 1) != 0)) break;
        if (++c > SPIN_LIMIT) __trap();
      }
#pragma unroll
      for (int i = 0; i < 4; i++) {
        asm volatile("st.shared.u32 [%0], %1;" ::"r"(misc + MS_RL + i * 128 + (lane >> 4) * 64 + ((lane >> 1) & 3) * 16 + ((lane >> 3) & 1) * 8 + (lane & 1) * 4), "r"(v[i].x) : "memory");
        asm volatile("st.shared.v4.u32 [%0], {%1,%2,%3,%3};" ::"r"(misc + MS_EXT + (i * 32 + lane) * 16), "r"(__byte_perm(v[i].y, 0, 0x1010)), "r"(v[i].y), "r"(0) : "memory");
      }
      asm volatile("fence.proxy.async.shared::cta;" ::: "memory");
      mbar_arrive(misc + B_STAT);
      if (lane == 0) TSX(4, 3);
#pragma unroll 1
      for (int m = 0; m < 4; m++) {
        nb_sync(m < 3 ? m : 14, m ? 160 : 288);
        while (ld_ll32(g_cnt + chunk * 32 + m) != e * 64) if (++c > SPIN_LIMIT) __trap();
        __syncwarp();
        warp_arrive<1>(misc + B_RDY + 8 * m);
        if (lane == 0) TSX(4, 8 + m);
      }
    }
    if (W < 18) {
      __syncwarp();
      if (elect_one()) {
        const int h = W & 1;
        const uint4* src = g_act + (size_t)chunk * 38 * 1024 + th * 512 + h * 1024;
        const CUtensorMap* cm = h ? &maps.cim : &maps.cre;
#pragma unroll 1
        for (int r = 0; r < 5; r++) {
#pragma unroll
          for (int i = 0; i < 8; i += 2) {
            if (i == 6 && r == 4) break;
            const uint32_t bytes = (i == 4 && r == 4 && h) ? 4096 : 8192, full = misc + B_FULL + 8 * i + 8 * h;
            mbar_wait(misc + B_EMPTY + 8 * i + 8 * h, r & 1);
            mbar_expect(full, 16384 + bytes);
            if (r < 2)
              asm volatile("cp.async.bulk.tensor.2d.shared::cluster.global.mbarrier::complete_tx::bytes [%0], [%1, {%3,%4}], [%2];" ::"r"(sm + slotB(i) + h * 16384),
                           "l"(cm), "r"(full), "r"(r * 256 + i * 32), "r"(cq * 128) : "memory");
            else
              asm volatile("cp.async.bulk.tensor.3d.shared::cluster.global.mbarrier::complete_tx::bytes [%0], [%1, {%3,%4,%5}], [%2];" ::"r"(sm + slotB(i) + h * 16384),
                           "l"(&maps.w2), "r"(full), "r"(0), "r"(((r - 2) * 8 + i + h) * 64), "r"(cq * 2) : "memory");
            if (i == 0) { if (h == 0) TSX(4, 16 + r); mbar_wait(misc + B_RDY + 8 * max(r - 1, 0), 0); }
            asm volatile("cp.async.bulk.shared::cluster.global.mbarrier::complete_tx::bytes [%0], [%1], %2, [%3];" ::"r"(sm + slotA(i) + (i < 6 ? h * 8192 : h * 16384 + aoff)),
                         "l"(src + i * 1024), "r"(bytes), "r"(full) : "memory");
          }
          src += 8192;
        }
      }
    }
    TSW(4);
  }
}

typedef CUresult (*EncFn)(CUtensorMap*, CUtensorMapDataType, cuuint32_t, void*, const cuuint64_t*, const cuuint64_t*, const cuuint32_t*,
                          const cuuint32_t*, CUtensorMapInterleave, CUtensorMapSwizzle, CUtensorMapL2promotion, CUtensorMapFloatOOBfill);

void encode(EncFn enc, CUtensorMap* m, int rank, const void* ptr, const cuuint64_t* dims, const cuuint64_t* strides, const cuuint32_t* box,
            CUtensorMapSwizzle sw, CUtensorMapDataType ty = CU_TENSOR_MAP_DATA_TYPE_BFLOAT16) {
  cuuint32_t es[5] = {1, 1, 1, 1, 1};
  enc(m, ty, rank, const_cast<void*>(ptr), dims, strides, box, es, CU_TENSOR_MAP_INTERLEAVE_NONE, sw,
      PROMO, CU_TENSOR_MAP_FLOAT_OOB_FILL_NONE);
}

}

extern "C" void kernel_launch(void* const* d_in, const int* in_sizes, int n_in, void* d_out, int out_size) {
  static EncFn enc = nullptr;
  if (!enc) {
    void* f = nullptr;
    cudaDriverEntryPointQueryResult qr;
    cudaGetDriverEntryPoint("cuTensorMapEncodeTiled", &f, cudaEnableDefault, &qr);
    enc = (EncFn)f;
    cudaFuncSetAttribute(fused_kernel<false>, cudaFuncAttributeMaxDynamicSharedMemorySize, SM_TOTAL);
    cudaFuncSetAttribute(fused_kernel<true>, cudaFuncAttributeMaxDynamicSharedMemorySize, SM_TOTAL);
  }
  Params p;
  p.x = (const bf16*)d_in[0];
  p.lam_re = (const bf16*)d_in[1]; p.lam_im = (const bf16*)d_in[2];
  p.swapB = (const char*)d_in[4] < (const char*)d_in[3];
  p.b_lo = (const bf16*)d_in[p.swapB ? 4 : 3]; p.b_hi = (const bf16*)d_in[p.swapB ? 3 : 4];
  p.log_dt = (const bf16*)d_in[7]; p.dskip = (const bf16*)d_in[8];
  p.w1 = (const bf16*)d_in[10]; p.b1 = (const bf16*)d_in[11];
  p.w2 = (const bf16*)d_in[12]; p.c_re = (const bf16*)d_in[5]; p.c_im = (const bf16*)d_in[6];
  p.out = (float*)d_out;
  p.dsw = dlo(0, 16) | ((unsigned long long)H128 << 32); p.dsw8k = dlo(0, 8192) | ((unsigned long long)H128 << 32);
  p.dns = dlo(0, 1024) | ((unsigned long long)HN128 << 32); p.zero = 0;
  p.dext = dlo(SM_MISC + MS_EXT, 0) | ((unsigned long long)HN128 << 32);
  Maps m;
  {
    cuuint64_t d[5] = {512, 2, 4, 16, 16}, s[4] = {1024, 32 * 1024, 2 * 1024, 128 * 1024};
    cuuint32_t bx[5] = {64, 2, 4, 16, 1};
    encode(enc, &m.x, 5, d_in[0], d, s, bx, CU_TENSOR_MAP_SWIZZLE_128B);
  }
  {
    cuuint64_t d[4] = {512, 8, 2, 64}, s[3] = {1024, (cuuint64_t)((const char*)p.b_hi - (const char*)p.b_lo), 8192};
    cuuint32_t bx[4] = {64, 8, 2, 8};
    encode(enc, &m.b, 4, p.b_lo, d, s, bx, CU_TENSOR_MAP_SWIZZLE_128B);
  }
  {
    cuuint64_t d[2] = {1376, 512}, s[1] = {2752};
    cuuint32_t bx[2] = {64, 128};
    encode(enc, &m.w1, 2, p.w1, d, s, bx, CU_TENSOR_MAP_SWIZZLE_128B);
  }
  {
    cuuint64_t d[3] = {64, 1376, 8}, s[2] = {1024, 128};
    cuuint32_t bx[3] = {64, 64, 2};
    encode(enc, &m.w2, 3, p.w2, d, s, bx, CU_TENSOR_MAP_SWIZZLE_128B);
  }
  {
    cuuint64_t d[2] = {512, 512}, s[1] = {1024};
    cuuint32_t bx[2] = {64, 128};
    encode(enc, &m.cre, 2, p.c_re, d, s, bx, CU_TENSOR_MAP_SWIZZLE_128B);
    encode(enc, &m.cim, 2, p.c_im, d, s, bx, CU_TENSOR_MAP_SWIZZLE_128B);
  }
  {
    cuuint64_t d[5] = {512, 16, 2, 4, 16}, s[4] = {2 * 2048, 2048, 32 * 2048, 128 * 2048};
    cuuint32_t bx[5] = {32, 2, 2, 4, 1};
    encode(enc, &m.out, 5, d_out, d, s, bx, CU_TENSOR_MAP_SWIZZLE_128B, CU_TENSOR_MAP_DATA_TYPE_FLOAT32);
  }
  if (p.swapB) fused_kernel<true><<<128, 640, SM_TOTAL>>>(m, p);
  else fused_kernel<false><<<128, 640, SM_TOTAL>>>(m, p);
}
```
